```python
import torch

def _softmax(x, axis=-1):
    return torch.softmax(x, dim=axis)
def _gelu(x):
    return torch.nn.functional.gelu(x, approximate="tanh")
def _silu(x):
    return torch.nn.functional.silu(x)
def _sigmoid(x):
    return torch.sigmoid(x)
def _layernorm(x, axis=-1, eps=1e-5):
    m = x.mean(dim=axis, keepdim=True)
    v = x.var(dim=axis, keepdim=True, unbiased=False)
    return (x - m) / torch.sqrt(v + eps)
def _scatter_add(tgt, idx, src, axis=0):
    return tgt.clone().index_add_(axis, idx, src)
def _segment_sum(src, seg, n):
    out = torch.zeros((n,) + src.shape[1:], dtype=src.dtype)
    return out.index_add_(0, seg, src)
def _pad(x, pw):
    flat = tuple(v for pair in reversed(pw) for v in pair)
    return torch.nn.functional.pad(x, flat)

kernel_name = 'concat_heads__mha_block_cached__gqa_block_cached__near_ridge'

def setup_inputs():

    _w = (lambda a: (lambda t: t.to(torch.bfloat16) if t.is_floating_point() else t)(torch.as_tensor(a)))
    def _A_setup():
        B, Sq, D = 8, 128, 512
        H, Sk, Dh = 32, 128, 128
        return {
            "x": _w((lambda *s: torch.randn(*s, dtype=torch.bfloat16) * 0.8)(B, Sq, D)),
            "k_cache": _w((lambda *s: torch.randn(*s, dtype=torch.bfloat16) * 0.8)(B, H, Sk, Dh)),
            "v_cache": _w((lambda *s: torch.randn(*s, dtype=torch.bfloat16) * 0.05)(B, H, Sk, Dh)),
            "wq": _w((lambda *s: torch.randn(*s, dtype=torch.bfloat16) * 0.8)(D, H * Dh) * (D ** -0.5)),
            "wo": _w((lambda *s: torch.randn(*s, dtype=torch.bfloat16) * 0.05)(H * Dh, D) * ((H * Dh) ** -0.5)),
        }
    _A_in = _A_setup()

    def _B_setup():
        B, Sq, D = 8, 128, 512
        Hq, Hkv, Sk, Dh = 32, 32, 128, 128
        assert Hq % Hkv == 0, (Hq, Hkv)
        return {
            "x": _w((lambda *s: torch.randn(*s, dtype=torch.bfloat16) * 0.8)(B, Sq, D)),
            "k_cache": _w((lambda *s: torch.randn(*s, dtype=torch.bfloat16) * 0.8)(B, Hkv, Sk, Dh)),
            "v_cache": _w((lambda *s: torch.randn(*s, dtype=torch.bfloat16) * 0.05)(B, Hkv, Sk, Dh)),
            "wq": _w((lambda *s: torch.randn(*s, dtype=torch.bfloat16) * 0.8)(D, Hq * Dh) * (D ** -0.5)),
            "wo": _w((lambda *s: torch.randn(*s, dtype=torch.bfloat16) * 0.05)(Hq * Dh, D) * ((Hq * Dh) ** -0.5)),
        }
    _B_in = _B_setup()

    return {
        "A_x": _A_in["x"],
        "A_k_cache": _A_in["k_cache"],
        "A_v_cache": _A_in["v_cache"],
        "A_wq": _A_in["wq"],
        "A_wo": _A_in["wo"],
        "B_x": _B_in["x"],
        "B_k_cache": _B_in["k_cache"],
        "B_v_cache": _B_in["v_cache"],
        "B_wq": _B_in["wq"],
        "B_wo": _B_in["wo"],
    }

def reference(A_x, A_k_cache, A_v_cache, A_wq, A_wo, B_x, B_k_cache, B_v_cache, B_wq, B_wo):
    def _A_ref(x, k_cache, v_cache, wq, wo):
        B, Sq, D = x.shape
        H, Dh = 32, 128
        q = (lambda x, *d: x.permute(*d))((x @ wq).reshape(B, Sq, H, Dh), 0, 2, 1, 3)
        scores = torch.einsum("bhqd,bhkd->bhqk", q, k_cache) * (Dh ** -0.5)
        p = _softmax(scores, axis=-1)
        o = torch.einsum("bhqk,bhkd->bhqd", p, v_cache)
        return (lambda x, *d: x.permute(*d))(o, 0, 2, 1, 3).reshape(B, Sq, H * Dh) @ wo

    def _B_ref(x, k_cache, v_cache, wq, wo):
        B, Sq, D = x.shape
        Hq, Dh = 32, 128
        Hkv = k_cache.shape[1]
        rep = Hq // Hkv
        q = (lambda x, *d: x.permute(*d))((x @ wq).reshape(B, Sq, Hq, Dh), 0, 2, 1, 3)
        k = (lambda x, n, axis: torch.repeat_interleave(x, n, dim=axis))(k_cache, rep, axis=1)
        v = (lambda x, n, axis: torch.repeat_interleave(x, n, dim=axis))(v_cache, rep, axis=1)
        scores = torch.einsum("bhqd,bhkd->bhqk", q, k) * (Dh ** -0.5)
        p = _softmax(scores, axis=-1)
        o = torch.einsum("bhqk,bhkd->bhqd", p, v)
        return (lambda x, *d: x.permute(*d))(o, 0, 2, 1, 3).reshape(B, Sq, Hq * Dh) @ wo

    a = _A_ref(A_x, A_k_cache, A_v_cache, A_wq, A_wo)
    b = _B_ref(B_x, B_k_cache, B_v_cache, B_wq, B_wo)
    return torch.concatenate([a, b], axis=-1)
```

```cpp
#include <cuda_runtime.h>
#include <cuda_bf16.h>
#include <cuda.h>
#include <stdint.h>
#include <type_traits>

namespace {

constexpr int SLOT_BYTES = 16384;
constexpr int PAIR_BYTES = 2 * SLOT_BYTES;
constexpr int NPAIR = 7;
constexpr int NTHREADS = 384;

constexpr int F_X = 0;
constexpr int F_WQ = 8;
constexpr int F_KV = 40;
constexpr int F_WO = 48;
constexpr int NFILL = 64;
constexpr int B_ZEROED = 0;
#define N_EARLY 1
__host__ __device__ constexpr int full_off(int f) {
    return 8 * (f < F_X + N_EARLY ? 2 * NFILL + f : (f >= F_WQ && f < F_WQ + 2 * N_EARLY) ? 2 * NFILL + 4 + f - F_WQ : f);
}
constexpr int SMEM_BYTES = NPAIR * PAIR_BYTES + (2 * NFILL + 12) * 8;

struct Params {
    CUtensorMap x[2], k[2], v[2], wq[2], wo[2], out;
    const __nv_bfloat16* xp[2];
    const __nv_bfloat16* wqp[2];
    const __nv_bfloat16* kp[2];
    const __nv_bfloat16* vp[2];
    const __nv_bfloat16* wop[2];
    __nv_bfloat16* outp;
    int zero;
};

__device__ unsigned int g_zero_cnt[16 * 32];

#define TS(role, i) do {} while (0)
#define TSG(role, i) do {} while (0)
#define TS_EXTRA 0

__device__ __forceinline__ uint32_t s2u(const void* p) { return (uint32_t)__cvta_generic_to_shared(p); }

__device__ __forceinline__ void mbar_init(uint32_t b, int c) {
    asm volatile("mbarrier.init.shared::cta.b64 [%0], %1;" ::"r"(b), "r"(c));
}
__device__ __forceinline__ void mbar_expect(uint32_t b, int bytes) {
    asm volatile("mbarrier.arrive.expect_tx.shared::cta.b64 _, [%0], %1;" ::"r"(b), "r"(bytes) : "memory");
}
__device__ __forceinline__ void mbar_wait(uint32_t b) {
    uint32_t ok;
    int it = 0;
    do {
        asm volatile(
            "{\n.reg .pred p;\n"
            "mbarrier.try_wait.parity.shared::cta.b64 p, [%1], 0;\n"
            "selp.u32 %0, 1, 0, p;\n}"
            : "=r"(ok) : "r"(b) : "memory");
    } while (!ok && ++it < (1 << 16));
}
__device__ __forceinline__ uint32_t mbar_test(uint32_t b) {
    uint32_t ok;
    asm volatile(
        "{\n.reg .pred p;\n"
        "mbarrier.test_wait.parity.shared::cta.b64 p, [%1], 0;\n"
        "selp.u32 %0, 1, 0, p;\n}"
        : "=r"(ok) : "r"(b) : "memory");
    return ok;
}
__device__ __forceinline__ void mbar_wait_if(uint32_t ok, uint32_t b) {
    if (!ok) mbar_wait(b);
}
__device__ __forceinline__ void mbar_arrive(uint32_t b) {
    asm volatile("mbarrier.arrive.shared::cta.b64 _, [%0];" ::"r"(b) : "memory");
}
__device__ __forceinline__ void mbar_arrive_n(uint32_t b, int n) {
    asm volatile("mbarrier.arrive.shared::cta.b64 _, [%0], %1;" ::"r"(b), "r"(n) : "memory");
}
__device__ __forceinline__ bool elect_one() {
    uint32_t p;
    asm volatile("{\n.reg .pred p;\nelect.sync _|p, 0xffffffff;\nselp.u32 %0, 1, 0, p;\n}" : "=r"(p));
    return p;
}
__device__ __forceinline__ void mbar_arrive_cluster(uint32_t b, uint32_t cta) {
    asm volatile(
        "{\n.reg .b32 r;\nmapa.shared::cluster.u32 r, %0, %1;\n"
        "mbarrier.arrive.shared::cluster.b64 _, [r];\n}" ::"r"(b), "r"(cta) : "memory");
}

__device__ __forceinline__ void tma_load(uint32_t dst, const CUtensorMap* tm, uint32_t bar, int c0, int c1) {
    asm volatile(
        "cp.async.bulk.tensor.2d.shared::cluster.global.mbarrier::complete_tx::bytes [%0], [%1, {%3, %4}], [%2];"
        ::"r"(dst), "l"(tm), "r"(bar), "r"(c0), "r"(c1) : "memory");
}
__device__ __forceinline__ void tma_load_hint(uint32_t dst, const CUtensorMap* tm, uint32_t bar, int c0, int c1,
                                              uint64_t pol) {
    asm volatile(
        "cp.async.bulk.tensor.2d.shared::cluster.global.mbarrier::complete_tx::bytes.L2::cache_hint"
        " [%0], [%1, {%3, %4}], [%2], %5;"
        ::"r"(dst), "l"(tm), "r"(bar), "r"(c0), "r"(c1), "l"(pol) : "memory");
}
__device__ __forceinline__ void tma_load_mc(uint32_t dst, const CUtensorMap* tm, uint32_t bar, int c0, int c1) {
    asm volatile(
        "cp.async.bulk.tensor.2d.shared::cluster.global.mbarrier::complete_tx::bytes.multicast::cluster"
        " [%0], [%1, {%3, %4}], [%2], %5;"
        ::"r"(dst), "l"(tm), "r"(bar), "r"(c0), "r"(c1), "h"((uint16_t)3) : "memory");
}
__device__ __forceinline__ void tma_load3(uint32_t dst, const CUtensorMap* tm, uint32_t bar, int c1, int c2) {
    asm volatile(
        "cp.async.bulk.tensor.3d.shared::cluster.global.mbarrier::complete_tx::bytes [%0], [%1, {%3, %4, %5}], [%2];"
        ::"r"(dst), "l"(tm), "r"(bar), "r"(0), "r"(c1), "r"(c2) : "memory");
}
__device__ __forceinline__ void tma_load3_mc(uint32_t dst, const CUtensorMap* tm, uint32_t bar, int c1, int c2) {
    asm volatile(
        "cp.async.bulk.tensor.3d.shared::cluster.global.mbarrier::complete_tx::bytes.multicast::cluster"
        " [%0], [%1, {%3, %4, %5}], [%2], %6;"
        ::"r"(dst), "l"(tm), "r"(bar), "r"(0), "r"(c1), "r"(c2), "h"((uint16_t)3) : "memory");
}
__device__ __forceinline__ void tma_load3_mc_hint(uint32_t dst, const CUtensorMap* tm, uint32_t bar, int c1, int c2,
                                                  uint64_t pol) {
    asm volatile(
        "cp.async.bulk.tensor.3d.shared::cluster.global.mbarrier::complete_tx::bytes.multicast::cluster.L2::cache_hint"
        " [%0], [%1, {%3, %4, %5}], [%2], %6, %7;"
        ::"r"(dst), "l"(tm), "r"(bar), "r"(0), "r"(c1), "r"(c2), "h"((uint16_t)3), "l"(pol) : "memory");
}
__device__ __forceinline__ void tma_load_mc_hint(uint32_t dst, const CUtensorMap* tm, uint32_t bar, int c0, int c1,
                                                 uint64_t pol) {
    asm volatile(
        "cp.async.bulk.tensor.2d.shared::cluster.global.mbarrier::complete_tx::bytes.multicast::cluster.L2::cache_hint"
        " [%0], [%1, {%3, %4}], [%2], %5, %6;"
        ::"r"(dst), "l"(tm), "r"(bar), "r"(c0), "r"(c1), "h"((uint16_t)3), "l"(pol) : "memory");
}
__device__ __forceinline__ void tma_prefetch(const CUtensorMap* tm, int c0, int c1) {
    asm volatile("cp.async.bulk.prefetch.tensor.2d.L2.global [%0, {%1, %2}];" ::"l"(tm), "r"(c0), "r"(c1) : "memory");
}
__device__ __forceinline__ void bulk_prefetch(const void* p, int bytes) {
    asm volatile("cp.async.bulk.prefetch.L2.global [%0], %1;" ::"l"(p), "r"(bytes) : "memory");
}
__device__ __forceinline__ void tma_reduce_add(const CUtensorMap* tm, uint32_t src, int c0, int c1) {
    asm volatile("cp.reduce.async.bulk.tensor.2d.global.shared::cta.add.tile.bulk_group [%0, {%2, %3}], [%1];"
                 ::"l"(tm), "r"(src), "r"(c0), "r"(c1) : "memory");
}

constexpr uint32_t SMEM_BASE = 1024;
__host__ __device__ constexpr uint64_t mkdesc(uint32_t off, uint32_t lbo, uint32_t sbo) {
    return (uint64_t)(((SMEM_BASE + off) & 0x3FFFF) >> 4) | ((uint64_t)(lbo >> 4) << 16) |
           ((uint64_t)(sbo >> 4) << 32) | (1ull << 62);
}
__device__ __forceinline__ void sched_fence(uint32_t zero) {
    asm volatile("{\n.reg .pred p;\nSF:\nsetp.ne.u32 p, %0, 0;\n@p nanosleep.u32 20;\n@p bra SF;\n}" ::"r"(zero) : "memory");
}
__device__ __forceinline__ void wg_fence() { asm volatile("wgmma.fence.sync.aligned;" ::: "memory"); }
__device__ __forceinline__ void wg_commit() { asm volatile("wgmma.commit_group.sync.aligned;" ::: "memory"); }
template <int N> __device__ __forceinline__ void wg_wait() {
    asm volatile("wgmma.wait_group.sync.aligned %0;" ::"n"(N) : "memory");
}

#define R8(a, i) "+f"(a[i]), "+f"(a[i + 1]), "+f"(a[i + 2]), "+f"(a[i + 3]), "+f"(a[i + 4]), "+f"(a[i + 5]), "+f"(a[i + 6]), "+f"(a[i + 7])
#define R32(a, i) R8(a, i), R8(a, i + 8), R8(a, i + 16), R8(a, i + 24)

__device__ __forceinline__ void wgmma_ss_n256_tb(float (&d)[128], uint64_t da, uint64_t db, int acc) {
    asm volatile(
        "{\n.reg .pred p;\nsetp.ne.b32 p, %130, 0;\n"
        "wgmma.mma_async.sync.aligned.m64n256k16.f32.bf16.bf16 "
        "{%0,%1,%2,%3,%4,%5,%6,%7,%8,%9,%10,%11,%12,%13,%14,%15,%16,%17,%18,%19,%20,%21,%22,%23,%24,%25,%26,%27,%28,%29,%30,%31,"
        "%32,%33,%34,%35,%36,%37,%38,%39,%40,%41,%42,%43,%44,%45,%46,%47,%48,%49,%50,%51,%52,%53,%54,%55,%56,%57,%58,%59,%60,%61,%62,%63,"
        "%64,%65,%66,%67,%68,%69,%70,%71,%72,%73,%74,%75,%76,%77,%78,%79,%80,%81,%82,%83,%84,%85,%86,%87,%88,%89,%90,%91,%92,%93,%94,%95,"
        "%96,%97,%98,%99,%100,%101,%102,%103,%104,%105,%106,%107,%108,%109,%110,%111,%112,%113,%114,%115,%116,%117,%118,%119,%120,%121,%122,%123,%124,%125,%126,%127},"
        " %128, %129, p, 1, 1, 0, 1;\n}"
        : R32(d, 0), R32(d, 32), R32(d, 64), R32(d, 96)
        : "l"(da), "l"(db), "r"(acc));
}
template <int TB>
__device__ __forceinline__ void wgmma_rs_n128(float (&d)[64], uint32_t a0, uint32_t a1, uint32_t a2, uint32_t a3,
                                              uint64_t db, int acc) {
    asm volatile(
        "{\n.reg .pred p;\nsetp.ne.b32 p, %69, 0;\n"
        "wgmma.mma_async.sync.aligned.m64n128k16.f32.bf16.bf16 "
        "{%0,%1,%2,%3,%4,%5,%6,%7,%8,%9,%10,%11,%12,%13,%14,%15,%16,%17,%18,%19,%20,%21,%22,%23,%24,%25,%26,%27,%28,%29,%30,%31,"
        "%32,%33,%34,%35,%36,%37,%38,%39,%40,%41,%42,%43,%44,%45,%46,%47,%48,%49,%50,%51,%52,%53,%54,%55,%56,%57,%58,%59,%60,%61,%62,%63},"
        " {%64,%65,%66,%67}, %68, p, 1, 1, %70;\n}"
        : R32(d, 0), R32(d, 32)
        : "r"(a0), "r"(a1), "r"(a2), "r"(a3), "l"(db), "r"(acc), "n"(TB));
}

template <int TB>
__device__ __forceinline__ void wgmma_ss_n128(float (&d)[64], uint64_t da, uint64_t db, int acc) {
    asm volatile(
        "{\n.reg .pred p;\nsetp.ne.b32 p, %66, 0;\n"
        "wgmma.mma_async.sync.aligned.m64n128k16.f32.bf16.bf16 "
        "{%0,%1,%2,%3,%4,%5,%6,%7,%8,%9,%10,%11,%12,%13,%14,%15,%16,%17,%18,%19,%20,%21,%22,%23,%24,%25,%26,%27,%28,%29,%30,%31,"
        "%32,%33,%34,%35,%36,%37,%38,%39,%40,%41,%42,%43,%44,%45,%46,%47,%48,%49,%50,%51,%52,%53,%54,%55,%56,%57,%58,%59,%60,%61,%62,%63},"
        " %64, %65, p, 1, 1, 0, %67;\n}"
        : R32(d, 0), R32(d, 32)
        : "l"(da), "l"(db), "r"(acc), "n"(TB));
}

__device__ __forceinline__ void wgmma_rs_n64(float (&d)[32], uint32_t a0, uint32_t a1, uint32_t a2, uint32_t a3,
                                             uint64_t db, int acc) {
    asm volatile(
        "{\n.reg .pred p;\nsetp.ne.b32 p, %37, 0;\n"
        "wgmma.mma_async.sync.aligned.m64n64k16.f32.bf16.bf16 "
        "{%0,%1,%2,%3,%4,%5,%6,%7,%8,%9,%10,%11,%12,%13,%14,%15,%16,%17,%18,%19,%20,%21,%22,%23,%24,%25,%26,%27,%28,%29,%30,%31},"
        " {%32,%33,%34,%35}, %36, p, 1, 1, 1;\n}"
        : R32(d, 0)
        : "r"(a0), "r"(a1), "r"(a2), "r"(a3), "l"(db), "r"(acc));
}
__device__ __forceinline__ void wgmma_ss_n64(float (&d)[32], uint64_t da, uint64_t db) {
    asm volatile(
        "wgmma.mma_async.sync.aligned.m64n64k16.f32.bf16.bf16 "
        "{%0,%1,%2,%3,%4,%5,%6,%7,%8,%9,%10,%11,%12,%13,%14,%15,%16,%17,%18,%19,%20,%21,%22,%23,%24,%25,%26,%27,%28,%29,%30,%31},"
        " %32, %33, 1, 1, 1, 0, 1;"
        : R32(d, 0)
        : "l"(da), "l"(db));
}

__device__ __forceinline__ void stmatrix_x4(uint32_t addr, uint32_t r0, uint32_t r1, uint32_t r2, uint32_t r3) {
    asm volatile("stmatrix.sync.aligned.m8n8.x4.shared.b16 [%0], {%1,%2,%3,%4};"
                 ::"r"(addr), "r"(r0), "r"(r1), "r"(r2), "r"(r3) : "memory");
}

__device__ __forceinline__ uint32_t pack_bf16(float lo, float hi) {
    uint32_t r;
    asm("cvt.rn.bf16x2.f32 %0, %1, %2;" : "=r"(r) : "f"(hi), "f"(lo));
    return r;
}
__device__ __forceinline__ float ex2(float x) {
    float y;
    asm volatile("ex2.approx.ftz.f32 %0, %1;" : "=f"(y) : "f"(x));
    return y;
}

__device__ __forceinline__ float rcp(float x) {
    float y;
    asm("rcp.approx.ftz.f32 %0, %1;" : "=f"(y) : "f"(x));
    return y;
}

__host__ __device__ constexpr int wq_slot(int j) { return 8 + (j + 4) % 6; }
__host__ __device__ constexpr int kv_pair(int u) { return u < 2 ? u : u < 5 ? u + 2 : u < 7 ? u - 5 : 6; }
__host__ __device__ constexpr int wo_pair(int v) { return (v & 3) < 2 ? 4 + (v & 3) : (v & 3) - 2; }
__host__ __device__ constexpr int q_pair(int h) { return h; }
__host__ __device__ constexpr int o_pair(int h) { return h + 1; }
constexpr int STAGE_PAIR = 6;
__host__ __device__ constexpr int k_idx(int h) { return h == 0 ? 0 : 2 * h - 1; }
__host__ __device__ constexpr int v_idx(int h) { return h == 3 ? 7 : 2 * h + 2; }
__host__ __device__ constexpr int kv_pred(int u) {
    return u < 2 ? F_WQ + 19 + 4 * u : u < 5 ? F_WQ + 23 + 2 * u : u < 7 ? F_KV + u - 5 : F_KV + 4;
}
__host__ __device__ constexpr int wo_pred(int v) { return v < 2 ? F_KV + 2 + v : v < 4 ? F_KV + 3 + v : F_WO + v - 4; }
__host__ __device__ constexpr int rel_kind(int f) {
    return f < F_WQ ? 0
         : f < F_KV ? ((f - F_WQ) < 26 ? 2 : ((f - F_WQ) & 1))
         : f < F_WO ? (((f - F_KV) == 2 || (f - F_KV) == 3 || (f - F_KV) == 5 || (f - F_KV) == 6) ? 2 : 1)
         : ((f - F_WO) < 12 ? 2 : 0);
}

template <int F>
__device__ __forceinline__ void release(uint32_t empty_base, bool elected, uint32_t rank) {
    if (rel_kind(F) == 0) return;
    if (elected) {
        if (rel_kind(F) == 2) {
            mbar_arrive(empty_base + F * 8);
            mbar_arrive_cluster(empty_base + F * 8, rank ^ 1);
        } else {
            mbar_arrive_n(empty_base + F * 8, 2);
        }
    }
}

template <int I, int N, typename Fn>
__device__ __forceinline__ void static_for(Fn&& f) {
    if constexpr (I < N) {
        f(std::integral_constant<int, I>{});
        static_for<I + 1, N>(f);
    }
}

__device__ __forceinline__ uint32_t ld_prefetch(const char* p) {
    uint32_t v;
    asm volatile("ld.volatile.global.L2::256B.b32 %0, [%1];" : "=r"(v) : "l"(p));
    return v;
}

template <int BOX_STRIDE, int J0 = 0, int J1 = 8>
__device__ __forceinline__ void store_tile(uint32_t base, const float* acc, float r0, float r1, int st_row, int st_chunk) {
#pragma unroll
    for (int jp = J0; jp < J1; jp++) {
        const uint32_t addr = base + (jp >> 2) * BOX_STRIDE + st_row * 128 + ((((2 * jp + st_chunk) & 7) ^ (st_row & 7)) << 4);
        stmatrix_x4(addr, pack_bf16(acc[8 * jp] * r0, acc[8 * jp + 1] * r0),
                    pack_bf16(acc[8 * jp + 2] * r1, acc[8 * jp + 3] * r1),
                    pack_bf16(acc[8 * jp + 4] * r0, acc[8 * jp + 5] * r0),
                    pack_bf16(acc[8 * jp + 6] * r1, acc[8 * jp + 7] * r1));
    }
}

constexpr float C_EXP = 0.08838834764831845f * 1.4426950408889634f;

__device__ __forceinline__ void row_max(const float (&s)[64], float& n0, float& n1) {
    int i0 = max(__float_as_int(s[0]), __float_as_int(s[1])), i1 = max(__float_as_int(s[2]), __float_as_int(s[3]));
    int i2 = max(__float_as_int(s[4]), __float_as_int(s[5])), i3 = max(__float_as_int(s[6]), __float_as_int(s[7]));
#pragma unroll
    for (int i = 1; i < 8; i++) {
        i0 = __vimax3_s32(i0, __float_as_int(s[8 * i]), __float_as_int(s[8 * i + 1]));
        i1 = __vimax3_s32(i1, __float_as_int(s[8 * i + 2]), __float_as_int(s[8 * i + 3]));
        i2 = __vimax3_s32(i2, __float_as_int(s[8 * i + 4]), __float_as_int(s[8 * i + 5]));
        i3 = __vimax3_s32(i3, __float_as_int(s[8 * i + 6]), __float_as_int(s[8 * i + 7]));
    }
    i0 = max(i0, i2);
    i1 = max(i1, i3);
    i0 = max(i0, __shfl_xor_sync(0xffffffffu, i0, 1));
    i1 = max(i1, __shfl_xor_sync(0xffffffffu, i1, 1));
    i0 = max(i0, __shfl_xor_sync(0xffffffffu, i0, 2));
    i1 = max(i1, __shfl_xor_sync(0xffffffffu, i1, 2));
    float m0 = __int_as_float(i0), m1 = __int_as_float(i1);
    if (__any_sync(0xffffffffu, (i0 | i1) < 0)) {
        m0 = fmaxf(s[0], s[1]);
        m1 = fmaxf(s[2], s[3]);
#pragma unroll
        for (int i = 1; i < 16; i++) {
            m0 = fmaxf(m0, fmaxf(s[4 * i], s[4 * i + 1]));
            m1 = fmaxf(m1, fmaxf(s[4 * i + 2], s[4 * i + 3]));
        }
        m0 = fmaxf(m0, __shfl_xor_sync(0xffffffffu, m0, 1));
        m1 = fmaxf(m1, __shfl_xor_sync(0xffffffffu, m1, 1));
        m0 = fmaxf(m0, __shfl_xor_sync(0xffffffffu, m0, 2));
        m1 = fmaxf(m1, __shfl_xor_sync(0xffffffffu, m1, 2));
    }
    n0 = -m0 * C_EXP;
    n1 = -m1 * C_EXP;
}
template <int I0, int I1>
__device__ __forceinline__ void row_exp(float (&s)[64], float n0, float n1, float& l0, float& l1) {
#pragma unroll
    for (int i = I0; i < I1; i++) {
        s[4 * i] = ex2(fmaf(s[4 * i], C_EXP, n0));
        s[4 * i + 1] = ex2(fmaf(s[4 * i + 1], C_EXP, n0));
        s[4 * i + 2] = ex2(fmaf(s[4 * i + 2], C_EXP, n1));
        s[4 * i + 3] = ex2(fmaf(s[4 * i + 3], C_EXP, n1));
        asm volatile("add.f32 %0, %0, %1;" : "+f"(l0) : "f"(s[4 * i] + s[4 * i + 1]));
        asm volatile("add.f32 %0, %0, %1;" : "+f"(l1) : "f"(s[4 * i + 2] + s[4 * i + 3]));
    }
}
__device__ __forceinline__ float quad_sum_rcp(float l) {
    l += __shfl_xor_sync(0xffffffffu, l, 1);
    l += __shfl_xor_sync(0xffffffffu, l, 2);
    return rcp(l);
}

#define FTS(i) do {} while (0)
template <int V> using IC = std::integral_constant<int, V>;

#define PF_LANES 16
#define PF_DEPTH 3
#define LAG3 0x400
#define ZERO_AT (F_WQ + 10)
#define KV_EVICT_FIRST 1
#define V3_AFTER 1
#define PF_DEPTH2 4
#define PF_SWITCH 7
#define LAG_STAGE 27
#define EARLY_DELAY 0
#define EARLY_IN_PROLOGUE 0
#define INIT_DELAY 100
#define ZERO_PACE 30
#define FENCE_AT (F_WQ + 16)
#define LAG_A 15
#define EV_MASK 0
#define K0_SPREAD 0
#define K0_AT 25
#define K1_AT 31
#define PF_START -1
#define WO_GATE 0
#define WO_GATE_BAR (F_KV + 7)
#define TAIL5 2
#define DEFER_QST 12
#define XA0 6
#define XB0 5
#define XA1 8
#define XA2 13

__global__ void __cluster_dims__(2, 1, 1) __launch_bounds__(NTHREADS, 1)
fused_attn_kernel(const __grid_constant__ Params P) {
    extern __shared__ __align__(1024) uint8_t smem_raw[];
    const uint32_t smem = s2u(smem_raw);
    const uint32_t full_base = smem + NPAIR * PAIR_BYTES;
    const uint32_t empty_base = full_base + NFILL * 8;

    const int tid = threadIdx.x;
    const uint32_t rank = blockIdx.x & 1;
    const int b = ((blockIdx.x >> 1) & 3) * 2 + rank;
    const int hg = (blockIdx.x >> 3) & 7;
    const int br = blockIdx.x >> 6;

    if ((smem & 0xFFFFFFu) != SMEM_BASE) return;
    if (tid == 0) { TS(0, 0); TSG(0, 62); }
    auto early_wq = [&](int j) {
        const uint32_t bar = full_base + full_off(F_WQ + j);
        mbar_expect(bar, SLOT_BYTES);
        tma_load3(smem + wq_slot(j) * SLOT_BYTES, &P.wq[br], bar, 32 * j, hg * 8);
        tma_load3(smem + wq_slot(j) * SLOT_BYTES + 8192, &P.wq[br], bar, 32 * j, hg * 8 + 2);
    };
    auto early_x = [&](int i) {
        const uint32_t bar = full_base + full_off(F_X + i);
        mbar_expect(bar, SLOT_BYTES);
        tma_load(smem + i * SLOT_BYTES, &P.x[br], bar, 64 * i, b * 128);
        tma_load(smem + i * SLOT_BYTES + 8192, &P.x[br], bar, 64 * i, b * 128 + 64);
    };
    if (tid < 32) {
        if (elect_one()) {
            mbar_init(full_base + full_off(F_WQ), 1);
            mbar_init(full_base + full_off(F_X), 1);
            asm volatile("fence.mbarrier_init.release.cluster;" ::: "memory");
            early_wq(0);
            early_x(0);
            TS(0, 9);
            mbar_init(full_base + full_off(F_WQ + 1), 1);
#pragma unroll
            for (int i = 1; i < N_EARLY; i++) {
                mbar_init(full_base + full_off(F_X + i), 1);
                mbar_init(full_base + full_off(F_WQ + 2 * i), 1);
                mbar_init(full_base + full_off(F_WQ + 2 * i + 1), 1);
            }
            asm volatile("fence.mbarrier_init.release.cluster;" ::: "memory");
        }
        __syncwarp();
    }
    const int lane = tid & 31;
    const int warp_id = __shfl_sync(0xffffffffu, tid >> 5, 0);
    const int wg = warp_id >> 2;

    if (warp_id >= 4) {
        if (INIT_DELAY) __nanosleep(INIT_DELAY);
        if (elect_one()) {
            const uint32_t o = (warp_id - 4) * 64;
#pragma unroll
            for (int i = 0; i < 8; i++) {
                mbar_init(full_base + o + i * 8, 1);
                mbar_init(empty_base + o + i * 8, 4);
            }
            asm volatile("fence.mbarrier_init.release.cluster;" ::: "memory");
            if (warp_id == 4) TS(1, 5);
        }
    }
    __syncwarp();
    asm volatile("barrier.cluster.arrive.relaxed.aligned;" ::: "memory");
    if (EARLY_IN_PROLOGUE && warp_id == 0) {
        if (EARLY_DELAY) __nanosleep(EARLY_DELAY);
        if (elect_one()) {
            early_wq(1);
#pragma unroll
            for (int i = 1; i < N_EARLY; i++) {
                early_wq(2 * i);
                early_x(i);
                early_wq(2 * i + 1);
            }
            TS(0, 8);
        }
        __syncwarp();
    }

    if (wg == 0) {
        asm volatile("setmaxnreg.dec.sync.aligned.u32 24;");
        if (!EARLY_IN_PROLOGUE && warp_id == 0) {
            if (EARLY_DELAY) __nanosleep(EARLY_DELAY);
            if (elect_one()) {
                early_wq(1);
#pragma unroll
                for (int i = 1; i < N_EARLY; i++) {
                    early_wq(2 * i);
                    early_x(i);
                    early_wq(2 * i + 1);
                }
                TS(0, 8);
            }
            __syncwarp();
        }
        const int kvrow0 = (b * 32 + hg * 4) * 128;
        if (warp_id == 1 || warp_id == 2) {
            constexpr int PARTS = 32 / PF_LANES;
            const int pw = warp_id - 1;
            const bool act = lane < PF_LANES;
            uint32_t v[PF_DEPTH2];
#pragma unroll
            for (int d = 0; d < PF_DEPTH2; d++) v[d] = 0;
            auto job = [&](auto nc, const char* p, int step) {
                static_for<0, PARTS>([&](auto qc) {
                    constexpr int idx = decltype(nc)::value * PARTS + decltype(qc)::value;
                    constexpr int sw = PF_SWITCH * PARTS / PF_DEPTH * PF_DEPTH;
                    constexpr int d = idx < sw ? idx % PF_DEPTH : (idx - sw + PF_DEPTH) % PF_DEPTH2;
                    if (act && v[d] != 0x9e3779b9u) v[d] = ld_prefetch(p + decltype(qc)::value * step);
                });
            };
            static_assert(PF_LANES == 16, "");
            const char* wq = (const char*)P.wqp[br] + (size_t)(b * 8 + ((lane >> 1) & 7)) * 8192 + hg * 1024 + (lane & 1) * 256;
            const char* xq = (const char*)P.xp[br] + (size_t)(b * 128 + hg * 16 + (lane & 15)) * 1024;
            asm volatile("barrier.cluster.wait.acquire.aligned;" ::: "memory");
            if (PF_START < 0) mbar_wait(full_base + full_off(F_X)); else __nanosleep(PF_START);
            job(IC<1>{}, pw ? xq + 512 : wq + 2 * 64 * 8192, pw ? 256 : 64 * 8192);
            job(IC<2>{}, wq + (4 + 2 * pw) * 64 * 8192, 64 * 8192);
            job(IC<3>{}, wq + 512 + (2 * pw) * 64 * 8192, 64 * 8192);
            job(IC<4>{}, wq + 512 + (4 + 2 * pw) * 64 * 8192, 64 * 8192);
            const char* kp = (const char*)P.kp[br] + (size_t)(kvrow0 + pw * 32 + lane) * 256;
            const char* vp = (const char*)P.vp[br] + (size_t)(kvrow0 + pw * 32 + lane) * 256;
            const char* wo = (const char*)P.wop[br] + (size_t)(hg * 512 + b * 64 + pw * 32 + lane) * 1024;
            static_for<0, 8>([&](auto uc) {
                constexpr int u = decltype(uc)::value;
                constexpr bool isv = (u == 7) || (u >= 2 && (u & 1) == 0);
                constexpr int h = isv ? (u == 7 ? 3 : (u >> 1) - 1) : ((u + 1) >> 1);
                constexpr int n0 = 5 + 2 * u + (u == 7 ? 1 : 0);
                if constexpr (u == 7) job(IC<n0 - 1>{}, wo + (hg & 3) * 256, PF_LANES * 1024);
                job(IC<n0>{}, (isv ? vp : kp) + h * 32768, PF_LANES * 256);
                job(IC<n0 + 1>{}, (isv ? vp : kp) + h * 32768 + 16384, PF_LANES * 256);
            });
            if (WO_GATE == 1) mbar_wait(full_base + (WO_GATE_BAR) * 8);
            job(IC<22>{}, wo + ((hg + 1) & 3) * 256, PF_LANES * 1024);
            if (WO_GATE == 2) mbar_wait(full_base + (WO_GATE_BAR) * 8);
            job(IC<23>{}, wo + ((hg + 2) & 3) * 256, PF_LANES * 1024);
            job(IC<24>{}, wo + ((hg + 3) & 3) * 256, PF_LANES * 1024);
#pragma unroll
            for (int d = 1; d < PF_DEPTH2; d++) v[0] ^= v[d];
            if (v[0] == 0x9e3779b9u && P.outp == nullptr) g_zero_cnt[1] = v[0];
            if (warp_id == 1 && lane == 0) TS(0, 5);
        } else {
            asm volatile("barrier.cluster.wait.acquire.aligned;" ::: "memory");
        }
        if (warp_id == 3) {
            mbar_wait(full_base + (ZERO_AT) * 8);
            __nv_bfloat16* o = P.outp + (size_t)(b * 128 + hg * 16) * 1024 + br * 512 + lane * 8;
#pragma unroll
            for (int i = 0; i < 32; i++) {
                *reinterpret_cast<uint4*>(o + (i >> 1) * 1024 + (i & 1) * 256) = make_uint4(0, 0, 0, 0);
                if (ZERO_PACE) __nanosleep(ZERO_PACE);
            }
            mbar_wait(full_base + (FENCE_AT) * 8);
            __threadfence();
            __syncwarp();
            if (lane == 0) {
                unsigned int target, cur;
                asm volatile("atom.add.relaxed.gpu.global.u32 %0, [%1], 1;"
                             : "=r"(target) : "l"(&g_zero_cnt[(br * 8 + b) * 32]) : "memory");
                target = (target & ~7u) + 8u;
                TS(0, 6);
                int it = 0;
                while (true) {
                    asm volatile("ld.acquire.gpu.global.u32 %0, [%1];"
                                 : "=r"(cur) : "l"(&g_zero_cnt[(br * 8 + b) * 32]) : "memory");
                    if ((int)(cur - target) >= 0 || ++it > (1 << 16)) break;
                    __nanosleep(200);
                }
                mbar_arrive_n(empty_base + B_ZEROED * 8, 4);
                TS(0, 7);
            }
        }
        if (warp_id == 0 && elect_one()) {
            TS(0, 1);
            uint64_t pol;
            asm volatile("createpolicy.fractional.L2::evict_first.b64 %0, 1.0;" : "=l"(pol));
            auto load_wq = [&](int j) {
                const uint32_t bar = full_base + (F_WQ + j) * 8;
                const uint32_t dst = smem + wq_slot(j) * SLOT_BYTES + rank * 8192;
                mbar_expect(bar, SLOT_BYTES);
                if (EV_MASK & 1) tma_load3_mc_hint(dst, &P.wq[br], bar, (j & 15) * 32, hg * 8 + (j >> 4) * 4 + rank * 2, pol);
                else tma_load3_mc(dst, &P.wq[br], bar, (j & 15) * 32, hg * 8 + (j >> 4) * 4 + rank * 2);
            };
            auto load_x = [&](int i) {
                const uint32_t bar = full_base + (F_X + i) * 8;
                mbar_expect(bar, SLOT_BYTES);
                if (EV_MASK & 2) {
                    tma_load_hint(smem + i * SLOT_BYTES, &P.x[br], bar, i * 64, b * 128, pol);
                    tma_load_hint(smem + i * SLOT_BYTES + 8192, &P.x[br], bar, i * 64, b * 128 + 64, pol);
                } else {
                    tma_load(smem + i * SLOT_BYTES, &P.x[br], bar, i * 64, b * 128);
                    tma_load(smem + i * SLOT_BYTES + 8192, &P.x[br], bar, i * 64, b * 128 + 64);
                }
            };
            auto load_kv = [&](int u) {
                const uint32_t bar = full_base + (F_KV + u) * 8;
                const uint32_t dst = smem + kv_pair(u) * PAIR_BYTES;
                const bool isv = (u == 7) || (u >= 2 && (u & 1) == 0);
                const int h = isv ? (u == 7 ? 3 : (u >> 1) - 1) : ((u + 1) >> 1);
                const int row = kvrow0 + h * 128;
                const CUtensorMap* tm = isv ? &P.v[br] : &P.k[br];
                mbar_wait(empty_base + kv_pred(u) * 8);
                mbar_expect(bar, PAIR_BYTES);
                tma_load_hint(dst, tm, bar, 0, row, pol);
                tma_load_hint(dst + (isv ? 16384 : 8192), tm, bar, 0, row + 64, pol);
                tma_load_hint(dst + (isv ? 8192 : 16384), tm, bar, 64, row, pol);
                tma_load_hint(dst + 24576, tm, bar, 64, row + 64, pol);
            };
            auto load_wo = [&](int v) {
                const uint32_t bar = full_base + (F_WO + v) * 8;
                const uint32_t dst = smem + wo_pair(v) * PAIR_BYTES + rank * 16384;
                const bool tall = TAIL5 && v >= 12;
                const int c0 = (((v >> 2) + hg) & 3) * 128 + (tall ? ((v >> 1) & 1) * 64 : 0);
                const int c1 = hg * 512 + (tall ? (v & 1) * 256 + rank * 128 : (v & 3) * 128 + rank * 64);
                mbar_wait(empty_base + wo_pred(v) * 8);
                mbar_expect(bar, PAIR_BYTES);
                if (EV_MASK & 4) {
                    tma_load_mc_hint(dst, &P.wo[br], bar, c0, c1, pol);
                    tma_load_mc_hint(dst + 8192, &P.wo[br], bar, c0 + 64, c1, pol);
                } else {
                    tma_load_mc(dst, &P.wo[br], bar, c0, c1);
                    tma_load_mc(dst + 8192, &P.wo[br], bar, tall ? c0 : c0 + 64, tall ? c1 + 64 : c1);
                }
            };

            for (int i = N_EARLY; i < 3; i++) {
                load_x(i);
                load_wq(2 * i);
                load_wq(2 * i + 1);
            }
            load_x(3);
            asm volatile("prefetch.tensormap [%0];" ::"l"(&P.k[br]) : "memory");
            asm volatile("prefetch.tensormap [%0];" ::"l"(&P.v[br]) : "memory");
            asm volatile("prefetch.tensormap [%0];" ::"l"(&P.wo[br]) : "memory");
            asm volatile("prefetch.tensormap [%0];" ::"l"(&P.out) : "memory");
#pragma unroll 1
            for (int j = 6; j < 32; j++) {
                mbar_wait(empty_base + (F_WQ + j - 6) * 8);
                load_wq(j);
                if (j < 15 && (j & 1) == 1) load_x((j + 1) >> 1);
                if (K0_SPREAD) {
                    if (j >= 25 && j < 29) {
                        const uint32_t bar = full_base + F_KV * 8;
                        if (j == 25) mbar_expect(bar, PAIR_BYTES);
                        const int q = j - 25;
                        tma_load_hint(smem + kv_pair(0) * PAIR_BYTES + q * 8192, &P.k[br], bar, (q >> 1) * 64,
                                      kvrow0 + (q & 1) * 64, pol);
                    }
                } else if (j == K0_AT) load_kv(0);
                if (j == K1_AT) load_kv(1);
            }
            TS(0, 2);
#pragma unroll 1
            for (int u = 2; u < 7; u++) load_kv(u);
#pragma unroll 1
            for (int v = 0; v < 16; v++) {
                load_wo(v);
                if (v == V3_AFTER) { load_kv(7); TS(0, 3); }
            }
            TS(0, 4);
        }
    } else {
        asm volatile("setmaxnreg.inc.sync.aligned.u32 240;");
        const int w = wg - 1;
        const int warp = warp_id & 3;
        const bool elected = (tid & 127) == 0;
        asm volatile("barrier.cluster.wait.acquire.aligned;" ::: "memory");
        if (elected) TS(1 + w, 0);

        const uint32_t zero = (uint32_t)P.zero;
        const uint64_t wdesc = (uint64_t)(w * (8192 >> 4));
        const int st_row = warp * 16 + ((lane >> 3) & 1) * 8 + (lane & 7);
        const int st_chunk = lane >> 4;
        auto turn_wait = [&]() { asm volatile("bar.sync 4, 256;" ::: "memory"); };
        auto turn_pass = [&]() { asm volatile("bar.arrive 4, 256;" ::: "memory"); };
        auto wg_bar = [&]() { asm volatile("bar.sync %0, 128;" ::"r"(1 + w) : "memory"); };

        float accA[64], accB[64];
        uint32_t pf[32];
        uint32_t qf[32];
        uint32_t q23[64];

        static_for<0, 2>([&](auto pc) {
            constexpr int p = decltype(pc)::value;
            float acc[128];
            static_for<0, 16>([&](auto ic) {
                constexpr int i = decltype(ic)::value;
                constexpr int j = p * 16 + i;
                if (p == 0 && (i & 1) == 0) mbar_wait(full_base + full_off(F_X + i / 2));
                mbar_wait(full_base + full_off(F_WQ + j));
                if (elected && i == 0) { TS(1 + w, 1 + 2 * p); if (w == 0) TSG(0, 50 + p); }
                if (elected && (i & 1) == 0) TS(1 + w, 44 + j / 2);
                if (j == LAG_A && w == 1) turn_wait();
                if (j == LAG_STAGE && w == 1) turn_wait();
                wg_fence();
                const uint64_t da = mkdesc((i / 2) * SLOT_BYTES + (i & 1) * 64, 16, 1024) + wdesc;
                const uint64_t db = mkdesc(wq_slot(j) * SLOT_BYTES, 4096, 1024);
#pragma unroll
                for (int kk = 0; kk < 2; kk++)
                    wgmma_ss_n256_tb(acc, da + kk * 2, db + kk * 128, (i | kk) != 0);
                wg_commit();
                if constexpr (i > 0) {
                    wg_wait<1>();
                    release<F_WQ + j - 1>(empty_base, elected, rank);
                }
                if (LAG_A >= 0 && j == 15 && w == 0) turn_pass();
                if (j == 31 && w == 0) turn_pass();
            });
            wg_wait<0>();
            release<F_WQ + p * 16 + 15>(empty_base, elected, rank);
            if (elected && p == 1) TS(1 + w, 6);
            if constexpr (p == 0) {
#pragma unroll
                for (int i = 0; i < 32; i++) {
                    pf[i] = pack_bf16(acc[2 * i], acc[2 * i + 1]);
                    qf[i] = pack_bf16(acc[64 + 2 * i], acc[64 + 2 * i + 1]);
                }
            } else {
                wg_bar();
#pragma unroll
                for (int jp = DEFER_QST; jp < 16; jp++) {
                    const uint32_t addr = smem + q_pair(2) * PAIR_BYTES + w * 8192 + (jp >> 2) * SLOT_BYTES + st_row * 128 +
                                          ((((2 * jp + st_chunk) & 7) ^ (st_row & 7)) << 4);
                    stmatrix_x4(addr, pack_bf16(acc[8 * jp], acc[8 * jp + 1]), pack_bf16(acc[8 * jp + 2], acc[8 * jp + 3]),
                                pack_bf16(acc[8 * jp + 4], acc[8 * jp + 5]), pack_bf16(acc[8 * jp + 6], acc[8 * jp + 7]));
                }
                sched_fence(zero);
#pragma unroll
                for (int i = 0; i < 4 * DEFER_QST; i++) {
                    q23[i] = pack_bf16(acc[2 * i], acc[2 * i + 1]);
                    asm volatile("" : "+r"(q23[i]));
                }
                sched_fence(zero);
            }
            if (elected) TS(1 + w, 2 + 2 * p);
        });

        auto part_s = [&](float (&s)[64], auto hc, auto k0c, auto k1c) {
            constexpr int h = decltype(hc)::value;
#pragma unroll
            for (int kk = decltype(k0c)::value; kk < decltype(k1c)::value; kk++) {
                const uint64_t db = mkdesc(kv_pair(k_idx(h)) * PAIR_BYTES + (kk >> 2) * SLOT_BYTES + (kk & 3) * 32, 16, 1024);
                if constexpr (h == 0) {
                    wgmma_rs_n128<0>(s, pf[4 * kk], pf[4 * kk + 1], pf[4 * kk + 2], pf[4 * kk + 3], db, kk != 0);
                } else if constexpr (h == 1) {
                    wgmma_rs_n128<0>(s, qf[4 * kk], qf[4 * kk + 1], qf[4 * kk + 2], qf[4 * kk + 3], db, kk != 0);
                } else {
                    const uint64_t da =
                        mkdesc(q_pair(h) * PAIR_BYTES + (kk >> 2) * SLOT_BYTES + (kk & 3) * 32, 16, 1024) + wdesc;
                    wgmma_ss_n128<0>(s, da, db, kk != 0);
                }
            }
            if (decltype(k1c)::value == 8) wg_commit();
        };
        auto issue_s = [&](float (&s)[64], auto hc) { part_s(s, hc, IC<0>{}, IC<8>{}); };
        auto part_pv = [&](float (&o)[64], auto hc, auto k0c, auto k1c) {
            constexpr int h = decltype(hc)::value;
#pragma unroll
            for (int kk = decltype(k0c)::value; kk < decltype(k1c)::value; kk++) {
                const uint64_t db =
                    mkdesc(kv_pair(v_idx(h)) * PAIR_BYTES + (kk >> 2) * SLOT_BYTES + (kk & 3) * 2048, 8192, 1024);
                wgmma_rs_n128<1>(o, pf[4 * kk], pf[4 * kk + 1], pf[4 * kk + 2], pf[4 * kk + 3], db, kk != 0);
            }
            if (decltype(k1c)::value == 8) wg_commit();
        };
        auto issue_pv = [&](float (&o)[64], auto hc) { part_pv(o, hc, IC<0>{}, IC<8>{}); };
        auto part_out = [&](float (&acc)[64], auto vc, auto k0c, auto k1c) {
            constexpr int v = decltype(vc)::value;
            constexpr int h = v & 3;
#pragma unroll
            for (int kk = decltype(k0c)::value; kk < decltype(k1c)::value; kk++) {
                const uint64_t db = mkdesc(wo_pair(v) * PAIR_BYTES + (kk >> 2) * SLOT_BYTES + (kk & 3) * 2048, 8192, 1024);
                if constexpr (h == 0) {
                    wgmma_rs_n128<1>(acc, qf[4 * kk], qf[4 * kk + 1], qf[4 * kk + 2], qf[4 * kk + 3], db, kk != 0);
                } else if constexpr (h == 3) {
                    wgmma_rs_n128<1>(acc, pf[4 * kk], pf[4 * kk + 1], pf[4 * kk + 2], pf[4 * kk + 3], db, 1);
                } else {
                    const uint64_t da =
                        mkdesc(o_pair(h) * PAIR_BYTES + (kk >> 2) * SLOT_BYTES + (kk & 3) * 32, 16, 1024) + wdesc;
                    wgmma_ss_n128<1>(acc, da, db, 1);
                }
            }
            if (decltype(k1c)::value == 8) wg_commit();
        };
        auto issue_out = [&](float (&acc)[64], auto vc) { part_out(acc, vc, IC<0>{}, IC<8>{}); };
        auto pack_p = [&](const float (&s)[64]) {
#pragma unroll
            for (int i = 0; i < 32; i++) pf[i] = pack_bf16(s[2 * i], s[2 * i + 1]);
        };
        auto pack_o = [&](const float (&o)[64], uint32_t (&f)[32], float r0, float r1) {
#pragma unroll
            for (int i = 0; i < 16; i++) {
                f[2 * i] = pack_bf16(o[4 * i] * r0, o[4 * i + 1] * r0);
                f[2 * i + 1] = pack_bf16(o[4 * i + 2] * r1, o[4 * i + 3] * r1);
            }
        };

        float (&s)[64] = accB;
        float (&o)[64] = accA;
        float (&acc0)[64] = accA;
        float (&acc1)[64] = accB;
        float r0, r1;
        uint32_t okv = 1;
        {
            if (elected) TS(1 + w, 7);
            mbar_wait(full_base + (F_KV + k_idx(0)) * 8);
            if (elected) { TS(1 + w, 8); if (w == 0) TSG(0, 52); }
            wg_fence();
            issue_s(s, IC<0>{});
            sched_fence(zero);
#pragma unroll
            for (int jp = 0; jp < DEFER_QST; jp++) {
                const uint32_t addr = smem + q_pair(2) * PAIR_BYTES + w * 8192 + (jp >> 2) * SLOT_BYTES + st_row * 128 +
                                      ((((2 * jp + st_chunk) & 7) ^ (st_row & 7)) << 4);
                stmatrix_x4(addr, q23[4 * jp], q23[4 * jp + 1], q23[4 * jp + 2], q23[4 * jp + 3]);
            }
            sched_fence(zero);
            wg_wait<0>();
            release<F_KV + k_idx(0)>(empty_base, elected, rank);
            float n0, n1, l0 = 0.f, l1 = 0.f;
            row_max(s, n0, n1);
            const uint32_t ok = mbar_test(full_base + (F_KV + k_idx(1)) * 8);
            row_exp<0, 16>(s, n0, n1, l0, l1);
            okv = mbar_test(full_base + (F_KV + v_idx(0)) * 8);
            pack_p(s);
            r0 = quad_sum_rcp(l0);
            r1 = quad_sum_rcp(l1);
            sched_fence(zero);
            if (elected) TS(1 + w, 10);
            mbar_wait_if(ok, full_base + (F_KV + k_idx(1)) * 8);
        }
        float q0, q1;
        static_for<0, 3>([&](auto hc) {
            constexpr int h = decltype(hc)::value;
            float n0, n1, l0 = 0.f, l1 = 0.f;
            if (elected) TS(1 + w, 11 + 4 * h);
            wg_fence();
            issue_s(s, IC<h + 1>{});
            if constexpr (h > 0) {
                sched_fence(zero);
                if constexpr (h == 1) {
                    pack_o(o, qf, q0, q1);
                } else {
                    store_tile<SLOT_BYTES>(smem + o_pair(1) * PAIR_BYTES + w * 8192, o, q0, q1, st_row, st_chunk);
                }
                sched_fence(zero);
            }
            mbar_wait_if(okv, full_base + (F_KV + v_idx(h)) * 8);
            wg_fence();
            issue_pv(o, hc);
            q0 = r0;
            q1 = r1;
            wg_wait<1>();
            release<F_KV + k_idx(h + 1)>(empty_base, elected, rank);
            if (elected) TS(1 + w, 12 + 4 * h);
            row_max(s, n0, n1);
            row_exp<0, (h < 2 ? XA0 : XB0)>(s, n0, n1, l0, l1);
            if constexpr (h == 2) {
                asm volatile("fence.proxy.async.shared::cta;" ::: "memory");
                wg_bar();
            }
            sched_fence(zero);
            wg_wait<0>();
            release<F_KV + v_idx(h)>(empty_base, elected, rank);
            if (elected) TS(1 + w, 13 + 4 * h);
            if constexpr (h < 2) {
                const uint32_t okk = mbar_test(full_base + (F_KV + k_idx(h + 2)) * 8);
                okv = mbar_test(full_base + (F_KV + v_idx(h + 1)) * 8);
                row_exp<XA0, 16>(s, n0, n1, l0, l1);
                pack_p(s);
                r0 = quad_sum_rcp(l0);
                r1 = quad_sum_rcp(l1);
                if constexpr (h == 0) {
                    asm volatile("fence.proxy.async.shared::cta;" ::: "memory");
                    wg_bar();
                }
                sched_fence(zero);
                if (elected) TS(1 + w, 14 + 4 * h);
                mbar_wait_if(okk, full_base + (F_KV + k_idx(h + 2)) * 8);
            } else {
                uint32_t ok = mbar_test(full_base + (F_WO + 0) * 8);
                store_tile<SLOT_BYTES>(smem + o_pair(2) * PAIR_BYTES + w * 8192, o, q0, q1, st_row, st_chunk);
                row_exp<XB0, XA1>(s, n0, n1, l0, l1);
                sched_fence(zero);
                mbar_wait_if(ok, full_base + (F_WO + 0) * 8);
                wg_fence();
                issue_out(acc0, IC<0>{});
                sched_fence(zero);
                ok = mbar_test(full_base + (F_WO + 1) * 8);
                row_exp<XA1, XA2>(s, n0, n1, l0, l1);
                sched_fence(zero);
                mbar_wait_if(ok, full_base + (F_WO + 1) * 8);
                issue_out(acc0, IC<1>{});
                sched_fence(zero);
                row_exp<XA2, 16>(s, n0, n1, l0, l1);
                pack_p(s);
                r0 = quad_sum_rcp(l0);
                r1 = quad_sum_rcp(l1);
                asm volatile("fence.proxy.async.shared::cta;" ::: "memory");
                wg_bar();
            }
        });

        const uint32_t stage = smem + STAGE_PAIR * PAIR_BYTES + w * SLOT_BYTES;
        auto reduce_box = [&](int cs, int q) {
            if (elected) {
                tma_reduce_add(&P.out, stage + q * 8192, br * 512 + ((cs + hg) & 3) * 128 + q * 64, b * 128 + w * 64);
                asm volatile("cp.async.bulk.commit_group;" ::: "memory");
            }
        };
        auto epilogue = [&](float (&acc)[64], auto cc) {
            constexpr int cs = decltype(cc)::value;
            if (elected) { TS(1 + w, 25 + 3 * cs); if (w == 0) TSG(0, 54 + cs); }
            store_tile<8192>(stage, acc, 1.f, 1.f, st_row, st_chunk);
            asm volatile("fence.proxy.async.shared::cta;" ::: "memory");
            wg_bar();
            if (cs == 3) {
                reduce_box(cs, 0);
                reduce_box(cs, 1);
            } else if (w == 0) {
                reduce_box(cs, 0);
            }
            if (elected) TS(1 + w, 26 + 3 * cs);
        };
        auto reduce_later = [&](int cs, int t) {
            if (t == 1) reduce_box(cs, 1 - w);
            if (t == 2 && w == 1) reduce_box(cs, 1);
        };
        auto stage_free = [&]() {
            if (elected) asm volatile("cp.async.bulk.wait_group.read 0;" ::: "memory");
            wg_bar();
        };
        auto out_stage = [&](float (&acc)[64], auto vc) {
            constexpr int v = decltype(vc)::value;
            mbar_wait(full_base + (F_WO + v) * 8);
            if (((LAG3 >> v) & 1) && w == 1) turn_wait();
            wg_fence();
            issue_out(acc, vc);
            wg_wait<1>();
            if (((LAG3 >> (v - 1)) & 1) && w == 0) turn_pass();
        };
        {
            if (elected) { TS(1 + w, 23); if (w == 0) TSG(0, 53); }
            wg_wait<1>();
            release<F_WO + 0>(empty_base, elected, rank);
            mbar_wait(full_base + (F_KV + v_idx(3)) * 8);
            if (elected) TS(1 + w, 24);
            wg_fence();
            issue_pv(accB, IC<3>{});
            wg_wait<1>();
            release<F_WO + 1>(empty_base, elected, rank);
            out_stage(acc0, IC<2>{});
            release<F_KV + v_idx(3)>(empty_base, elected, rank);
            pack_o(accB, pf, r0, r1);
        }
        out_stage(acc0, IC<3>{});
        release<F_WO + 2>(empty_base, elected, rank);
        out_stage(acc1, IC<4>{});
        release<F_WO + 3>(empty_base, elected, rank);
        mbar_wait(empty_base + (F_KV + v_idx(3)) * 8);
        if (elected) {
            mbar_wait(empty_base + B_ZEROED * 8);
            asm volatile("fence.proxy.async.global;" ::: "memory");
        }
        epilogue(acc0, IC<0>{});
        static_for<5, (TAIL5 ? 12 : 16)>([&](auto vc) {
            constexpr int v = decltype(vc)::value;
            if constexpr ((v >> 2) & 1) out_stage(acc1, vc); else out_stage(acc0, vc);
            release<F_WO + v - 1>(empty_base, elected, rank);
            reduce_later((v >> 2) - 1, v & 3);
            if constexpr ((v & 3) == 3) stage_free();
            if constexpr ((v & 3) == 0) {
                if constexpr ((v >> 2) & 1) epilogue(acc0, IC<(v >> 2) - 1>{}); else epilogue(acc1, IC<(v >> 2) - 1>{});
            }
        });
        {
            float ha[32], hb[32];
            auto half = [&](float (&hh)[32], auto vc, auto k0c, auto k1c) {
                constexpr int v = decltype(vc)::value;
#pragma unroll
                for (int k2 = decltype(k0c)::value; k2 < decltype(k1c)::value; k2++) {
                    const int h = (v & 1) * 2 + (k2 >> 3), kk = k2 & 7;
                    const uint64_t db = mkdesc(wo_pair(v) * PAIR_BYTES + (k2 >> 2) * 8192 + (k2 & 3) * 2048, 8192, 1024);
                    if (h == 0) {
                        wgmma_rs_n64(hh, qf[4 * kk], qf[4 * kk + 1], qf[4 * kk + 2], qf[4 * kk + 3], db, kk != 0);
                    } else if (h == 3) {
                        wgmma_rs_n64(hh, pf[4 * kk], pf[4 * kk + 1], pf[4 * kk + 2], pf[4 * kk + 3], db, 1);
                    } else {
                        wgmma_ss_n64(hh, mkdesc(o_pair(h) * PAIR_BYTES + (kk >> 2) * SLOT_BYTES + (kk & 3) * 32, 16, 1024) + wdesc, db);
                    }
                }
                wg_commit();
            };
            mbar_wait(full_base + (F_WO + 12) * 8);
            wg_fence();
            half(ha, IC<12>{}, IC<0>{}, IC<8>{});
            wg_wait<1>();
            release<F_WO + 11>(empty_base, elected, rank);
            if (elected) TS(1 + w, 31);
            store_tile<8192>(stage, acc0, 1.f, 1.f, st_row, st_chunk);
            asm volatile("fence.proxy.async.shared::cta;" ::: "memory");
            wg_bar();
            reduce_box(2, 0);
            half(ha, IC<12>{}, IC<8>{}, IC<16>{});
            mbar_wait(full_base + (F_WO + 13) * 8);
            reduce_box(2, 1);
            half(ha, IC<13>{}, IC<0>{}, IC<16>{});
            if (elected) asm volatile("cp.async.bulk.wait_group.read 1;" ::: "memory");
            wg_bar();
            mbar_wait(full_base + (F_WO + 14) * 8);
            half(hb, IC<14>{}, IC<0>{}, IC<8>{});
            wg_wait<1>();
            if (elected) TS(1 + w, 33);
            store_tile<8192, 0, 4>(stage, ha, 1.f, 1.f, st_row, st_chunk);
            asm volatile("fence.proxy.async.shared::cta;" ::: "memory");
            wg_bar();
            reduce_box(3, 0);
            half(hb, IC<14>{}, IC<8>{}, IC<16>{});
            mbar_wait(full_base + (F_WO + 15) * 8);
            if (TAIL5 == 2 && w == 1) turn_wait();
            half(hb, IC<15>{}, IC<0>{}, IC<16>{});
            if (TAIL5 == 2 && w == 0) turn_pass();
            if (elected) asm volatile("cp.async.bulk.wait_group.read 1;" ::: "memory");
            wg_bar();
            wg_wait<0>();
            if (elected) { TS(1 + w, 34); if (w == 0) TSG(0, 57); }
            store_tile<8192, 0, 4>(stage + 8192, hb, 1.f, 1.f, st_row, st_chunk);
            asm volatile("fence.proxy.async.shared::cta;" ::: "memory");
            wg_bar();
            reduce_box(3, 1);
            if (elected) TS(1 + w, 35);
        }
        if (elected) {
            asm volatile("cp.async.bulk.wait_group.read 0;" ::: "memory");
            TS(1 + w, 40);
            TSG(1 + w, 63);
        }
    }
}

#define L2_PROMO CU_TENSOR_MAP_L2_PROMOTION_NONE
typedef CUresult (*EncodeFn)(CUtensorMap*, CUtensorMapDataType, cuuint32_t, void*, const cuuint64_t*,
                             const cuuint64_t*, const cuuint32_t*, const cuuint32_t*, CUtensorMapInterleave,
                             CUtensorMapSwizzle, CUtensorMapL2promotion, CUtensorMapFloatOOBfill);

void make_map(EncodeFn enc, CUtensorMap* m, const void* ptr, uint64_t rows, uint64_t cols, uint32_t box_rows = 64) {
    cuuint64_t gd[2] = {cols, rows};
    cuuint64_t gs[1] = {cols * 2};
    cuuint32_t box[2] = {64, box_rows};
    cuuint32_t es[2] = {1, 1};
    enc(m, CU_TENSOR_MAP_DATA_TYPE_BFLOAT16, 2, const_cast<void*>(ptr), gd, gs, box, es,
        CU_TENSOR_MAP_INTERLEAVE_NONE, CU_TENSOR_MAP_SWIZZLE_128B, L2_PROMO,
        CU_TENSOR_MAP_FLOAT_OOB_FILL_NONE);
}

void make_map3(EncodeFn enc, CUtensorMap* m, const void* ptr, uint64_t rows, uint64_t cols, uint32_t box_rows,
               uint32_t blocks) {
    cuuint64_t gd[3] = {64, rows, cols / 64};
    cuuint64_t gs[2] = {cols * 2, 128};
    cuuint32_t box[3] = {64, box_rows, blocks};
    cuuint32_t es[3] = {1, 1, 1};
    enc(m, CU_TENSOR_MAP_DATA_TYPE_BFLOAT16, 3, const_cast<void*>(ptr), gd, gs, box, es,
        CU_TENSOR_MAP_INTERLEAVE_NONE, CU_TENSOR_MAP_SWIZZLE_128B, L2_PROMO,
        CU_TENSOR_MAP_FLOAT_OOB_FILL_NONE);
}

}

extern "C" void kernel_launch(void* const* d_in, const int* in_sizes, int n_in, void* d_out, int out_size) {
    (void)in_sizes; (void)n_in; (void)out_size;
    static EncodeFn enc = nullptr;
    if (!enc) {
        void* fn = nullptr;
        cudaDriverEntryPointQueryResult qr;
        cudaGetDriverEntryPoint("cuTensorMapEncodeTiled", &fn, cudaEnableDefault, &qr);
        enc = (EncodeFn)fn;
        cudaFuncSetAttribute(fused_attn_kernel, cudaFuncAttributeMaxDynamicSharedMemorySize, SMEM_BYTES + TS_EXTRA);
    }
    Params P;
    for (int br = 0; br < 2; br++) {
        void* const* in = d_in + br * 5;
        make_map(enc, &P.x[br], in[0], 1024, 512);
        make_map(enc, &P.k[br], in[1], 32768, 128);
        make_map(enc, &P.v[br], in[2], 32768, 128);
        make_map3(enc, &P.wq[br], in[3], 512, 4096, 32, 2);
        make_map(enc, &P.wo[br], in[4], 4096, 512);
        P.xp[br] = (const __nv_bfloat16*)in[0];
        P.wqp[br] = (const __nv_bfloat16*)in[3];
        P.kp[br] = (const __nv_bfloat16*)in[1];
        P.vp[br] = (const __nv_bfloat16*)in[2];
        P.wop[br] = (const __nv_bfloat16*)in[4];
    }
    make_map(enc, &P.out, d_out, 1024, 1024);
    P.outp = (__nv_bfloat16*)d_out;
    P.zero = 0;
    fused_attn_kernel<<<128, NTHREADS, SMEM_BYTES + TS_EXTRA, cudaStreamPerThread>>>(P);
}
```
